```python
import torch

def _softmax(x, axis=-1):
    return torch.softmax(x, dim=axis)
def _gelu(x):
    return torch.nn.functional.gelu(x, approximate="tanh")
def _silu(x):
    return torch.nn.functional.silu(x)
def _sigmoid(x):
    return torch.sigmoid(x)
def _layernorm(x, axis=-1, eps=1e-5):
    m = x.mean(dim=axis, keepdim=True)
    v = x.var(dim=axis, keepdim=True, unbiased=False)
    return (x - m) / torch.sqrt(v + eps)
def _scatter_add(tgt, idx, src, axis=0):
    return tgt.clone().index_add_(axis, idx, src)
def _segment_sum(src, seg, n):
    out = torch.zeros((n,) + src.shape[1:], dtype=src.dtype)
    return out.index_add_(0, seg, src)
def _pad(x, pw):
    flat = tuple(v for pair in reversed(pw) for v in pair)
    return torch.nn.functional.pad(x, flat)

kernel_name = 'standalone__gated_linear_recurrence__prompt'

def setup_inputs():

    _w = (lambda a: (lambda t: t.to(torch.bfloat16) if t.is_floating_point() else t)(torch.as_tensor(a)))
    B, H, T, D = 1, 16, 2048, 256
    return {
        "q": _w((lambda *s: torch.randn(*s, dtype=torch.bfloat16) * 0.05)(B, H, T, D)),
        "k": _w((lambda *s: torch.randn(*s, dtype=torch.bfloat16) * 0.05)(B, H, T, D)),
        "v": _w((lambda *s: torch.randn(*s, dtype=torch.bfloat16) * 0.05)(B, H, T, D)),
        "g": _w((lambda *s: torch.randn(*s, dtype=torch.bfloat16) * 0.8)(B, H, T, D)),
    }

def reference(q, k, v, g):
    B, H, T, D = q.shape
    scale = D ** -0.5
    a = _sigmoid(g)
    S = k[:, :, 0, :, None] * v[:, :, 0, None, :] * 0.0
    outs = []
    for t in range(T):
        S = a[:, :, t, :, None] * S + k[:, :, t, :, None] * v[:, :, t, None, :]
        ot = torch.einsum("bhd,bhde->bhe", q[:, :, t, :], S) * scale
        outs.append(ot)
    return torch.stack(outs, 2)
```

```cpp
#include <cuda_runtime.h>
#include <cuda_bf16.h>
#include <cuda.h>
#include <stdint.h>
#include <stdlib.h>

namespace {

constexpr int H_ = 16, T_ = 2048, D_ = 256, CH = 64, NCHUNK = T_ / CH;
constexpr int NST = 3;
constexpr int NVS = 2;
#define HINT 7
#define STAGGER 0
#define PFD 0
#define PSLEEP 20
#define DRY 1
#define OPT 4
#define SDELAY 1
#define XDEEP 1
#define PROBE 1
#define PRO 2
#define MC 1
#define PI_EARLY 2
constexpr int PANEL = 8192;

constexpr int ST_BYTES = 6 * PANEL;
constexpr int ST_Q = 0, ST_K = 2 * PANEL, ST_G = 4 * PANEL;
constexpr int ST_A = ST_G;
constexpr int ST_VEC = ST_G + PANEL;
constexpr int VEC_P1 = 0, VEC_P2 = 512, VEC_FLAG = 2048;
constexpr int OFF_INBOX = 0;
constexpr int OFF_ST = OFF_INBOX + 2 * PANEL;
constexpr int OFF_V = OFF_ST + NST * ST_BYTES;
constexpr int V_BYTES = 4 * PANEL;
constexpr int OFF_FBUF = OFF_V + NVS * V_BYTES;
constexpr int OFF_PD = OFF_FBUF + 1024;
constexpr int OFF_BAR = OFF_PD + 1024;
constexpr int SMEM_USED = OFF_BAR + 512;
constexpr int SMEM_ALLOC = SMEM_USED;
constexpr uint32_t SM_BASE = 1024;

constexpr int B_FULL = 0;
constexpr int B_QK = B_FULL + NST;
constexpr int B_A = B_QK + NST;
constexpr int B_EMPTY = B_A + NST;
constexpr int B_VFULL = B_EMPTY + NST;
constexpr int B_VFREE = B_VFULL + 8;
constexpr int B_INFULL = B_VFREE + 8;
constexpr int B_INFREE = B_INFULL + 2;
constexpr int B_PFREE = B_INFREE + 2;
constexpr int B_TAG = B_PFREE + 4;
static_assert((B_TAG + 2) * 8 <= 512, "barrier region");

constexpr float G_LIMIT = 9223372036854775808.0f;
constexpr float NLOG2E = -1.4426950408889634f;

constexpr int MAXSEG = 8;
constexpr int NSLOT = 12;
struct Seg {
    int8_t full;
    int8_t c0, c1;
    int8_t comb;
};
constexpr int MAXSEQ = 48;
struct Sched {
    Seg seg[8][MAXSEG];
    int nseg[8];
    int8_t seq[8][MAXSEQ];
    int8_t pub[2][NCHUNK];
};

__device__ uint4 g_state[H_ * NSLOT * 2 * 2 * 2 * 8 * 128];
__device__ unsigned int g_epoch[128];
__device__ float g_fb[128 * CH * 128];

#define TRACE_GT(i)
#define TRACE_DECL(role)
#define TRACE(tag)

__device__ __forceinline__ uint32_t smem_u32(const void* p) { return (uint32_t)__cvta_generic_to_shared(p); }
__device__ __forceinline__ void mbar_init(uint32_t a, uint32_t c) {
    asm volatile("mbarrier.init.shared::cta.b64 [%0], %1;" ::"r"(a), "r"(c));
}
__device__ __forceinline__ void mbar_expect_tx(uint32_t a, uint32_t b) {
    asm volatile("mbarrier.arrive.expect_tx.shared::cta.b64 _, [%0], %1;" ::"r"(a), "r"(b) : "memory");
}
__device__ __forceinline__ void mbar_arrive(uint32_t a) {
    asm volatile("mbarrier.arrive.shared::cta.b64 _, [%0];" ::"r"(a) : "memory");
}
__device__ __forceinline__ void mbar_arrive_remote(uint32_t a) {
    asm volatile("fence.release.sync_restrict::shared::cta.cluster;\n"
                 "mbarrier.arrive.relaxed.cluster.shared::cluster.b64 _, [%0];" ::"r"(a) : "memory");
}
constexpr int SPIN_LIMIT = 1 << 22;
#define PKT_AHEAD 0
__device__ __forceinline__ void spin_check(int it) {
    asm volatile("{.reg .pred p; setp.gt.s32 p, %0, %1; @p trap;}" ::"r"(it), "n"(SPIN_LIMIT));
}
#define MBAR_WAIT_ASM(SEM)                                                          \
    asm volatile("{\n"                                                              \
                 ".reg .pred P1;\n"                                                 \
                 ".reg .b32 c;\n"                                                   \
                 "mov.b32 c, 0;\n"                                                  \
                 "LAB_WAIT:\n"                                                      \
                 "mbarrier.try_wait.parity" SEM ".shared::cta.b64 P1, [%0], %1;\n"  \
                 "@P1 bra DONE;\n"                                                  \
                 "add.u32 c, c, 1;\n"                                               \
                 "setp.lt.u32 P1, c, 4194304;\n"                                    \
                 "@P1 bra LAB_WAIT;\n"                                              \
                 "trap;\n"                                                          \
                 "DONE:\n"                                                          \
                 "}" ::"r"(a), "r"(p) : "memory")
__device__ __forceinline__ void mbar_wait(uint32_t a, uint32_t p) { MBAR_WAIT_ASM(""); }
__device__ __forceinline__ void mbar_wait_cluster(uint32_t a, uint32_t p) {
    MBAR_WAIT_ASM(".relaxed.cluster");
    asm volatile("fence.acquire.sync_restrict::shared::cluster.cluster;" ::: "memory");
}
__device__ __forceinline__ void mbar_wait2(uint32_t a, uint32_t pa, uint32_t b, uint32_t pb) {
    asm volatile("{\n"
                 ".reg .pred P1, P2;\n"
                 ".reg .b32 c;\n"
                 "mov.b32 c, 0;\n"
                 "LAB_WAIT:\n"
                 "mbarrier.try_wait.parity.shared::cta.b64 P1, [%0], %1;\n"
                 "mbarrier.try_wait.parity.shared::cta.b64 P2, [%2], %3;\n"
                 "and.pred P1, P1, P2;\n"
                 "@P1 bra DONE;\n"
                 "add.u32 c, c, 1;\n"
                 "setp.lt.u32 P1, c, 4194304;\n"
                 "@P1 bra LAB_WAIT;\n"
                 "trap;\n"
                 "DONE:\n"
                 "}" ::"r"(a), "r"(pa), "r"(b), "r"(pb) : "memory");
}
__device__ __forceinline__ void mbar_wait3(uint32_t a, uint32_t pa, uint32_t b, uint32_t pb, uint32_t c, uint32_t pc) {
    asm volatile("{\n"
                 ".reg .pred P1, P2, P3;\n"
                 ".reg .b32 c;\n"
                 "mov.b32 c, 0;\n"
                 "LAB_WAIT:\n"
                 "mbarrier.try_wait.parity.shared::cta.b64 P1, [%0], %1;\n"
                 "mbarrier.try_wait.parity.shared::cta.b64 P2, [%2], %3;\n"
                 "mbarrier.try_wait.parity.shared::cta.b64 P3, [%4], %5;\n"
                 "and.pred P1, P1, P2;\n"
                 "and.pred P1, P1, P3;\n"
                 "@P1 bra DONE;\n"
                 "add.u32 c, c, 1;\n"
                 "setp.lt.u32 P1, c, 4194304;\n"
                 "@P1 bra LAB_WAIT;\n"
                 "trap;\n"
                 "DONE:\n"
                 "}" ::"r"(a), "r"(pa), "r"(b), "r"(pb), "r"(c), "r"(pc) : "memory");
}
__device__ __forceinline__ void fence_acq_cluster() { asm volatile("fence.acquire.sync_restrict::shared::cluster.cluster;" ::: "memory"); }
__device__ __forceinline__ bool elect_one() {
    uint32_t r;
    asm volatile("{.reg .pred p; elect.sync _|p, 0xffffffff; selp.b32 %0, 1, 0, p;}" : "=r"(r));
    return r != 0;
}
__device__ __forceinline__ uint32_t opaque_tid() { uint32_t r; asm volatile("mov.u32 %0, %%tid.x;" : "=r"(r)); return r; }
__device__ __forceinline__ uint32_t mapa(uint32_t a, uint32_t r) {
    uint32_t d;
    asm volatile("mapa.shared::cluster.u32 %0, %1, %2;" : "=r"(d) : "r"(a), "r"(r));
    return d;
}
__device__ __forceinline__ void fence_async() { asm volatile("fence.proxy.async.shared::cta;" ::: "memory"); }
template <int ID> __device__ __forceinline__ void bar_sync128() { asm volatile("bar.sync %0, 128;" ::"n"(ID) : "memory"); }
__device__ __forceinline__ void bar_sync_id(int id) { asm volatile("bar.sync %0, 128;" ::"r"(id) : "memory"); }
__device__ __forceinline__ void bar_arrive_id(int id) { asm volatile("bar.arrive %0, 128;" ::"r"(id) : "memory"); }
__device__ __forceinline__ bool bar_red_or1(bool v) {
    uint32_t r;
    asm volatile("{.reg .pred p, q; setp.ne.u32 q, %1, 0; bar.red.or.pred p, 1, 128, q; selp.b32 %0,1,0,p;}"
                 : "=r"(r) : "r"((uint32_t)v) : "memory");
    return __shfl_sync(0xffffffffu, r, 0);
}
constexpr uint64_t L2_NORMAL = 0x1000000000000000ull, L2_FIRST = 0x12F0000000000000ull;
__device__ __forceinline__ void tma_load3(uint32_t dst, const CUtensorMap* tm, uint32_t bar, int c0, int c1, int c2, uint64_t pol) {
    asm volatile("cp.async.bulk.tensor.3d.shared::cluster.global.mbarrier::complete_tx::bytes.L2::cache_hint [%0], [%1, {%3,%4,%5}], [%2], %6;"
                 ::"r"(dst), "l"(tm), "r"(bar), "r"(c0), "r"(c1), "r"(c2), "l"(pol) : "memory");
}
__device__ __forceinline__ void tma_load3_both(uint32_t dst, const CUtensorMap* tm, uint32_t bar, int c0, int c1, int c2, uint64_t pol) {
    asm volatile("cp.async.bulk.tensor.3d.shared::cluster.global.mbarrier::complete_tx::bytes.multicast::cluster.L2::cache_hint"
                 " [%0], [%1, {%3,%4,%5}], [%2], %7, %6;"
                 ::"r"(dst), "l"(tm), "r"(bar), "r"(c0), "r"(c1), "r"(c2), "l"(pol), "h"((uint16_t)3) : "memory");
}
__device__ __forceinline__ void tma_store3(const CUtensorMap* tm, uint32_t src, int c0, int c1, int c2) {
    asm volatile("cp.async.bulk.tensor.3d.global.shared::cta.bulk_group.L2::cache_hint [%0, {%2,%3,%4}], [%1], %5;"
                 ::"l"(tm), "r"(src), "r"(c0), "r"(c1), "r"(c2), "l"((HINT & 2) ? L2_FIRST : L2_NORMAL) : "memory");
}
__device__ __forceinline__ void l2_prefetch(const void* p) {
    asm volatile("cp.async.bulk.prefetch.L2.global [%0], %1;" ::"l"(p), "n"(CH / 2 * D_ * 2) : "memory");
}
__device__ __forceinline__ uint4 ld_pkt(const uint4* p) {
    uint4 v;
    asm volatile("{.reg .b128 x; .reg .b64 l, h; ld.relaxed.gpu.global.b128 x, [%4]; mov.b128 {l, h}, x; mov.b64 {%0,%1}, l; mov.b64 {%2,%3}, h;}"
                 : "=r"(v.x), "=r"(v.y), "=r"(v.z), "=r"(v.w) : "l"(p) : "memory");
    return v;
}
__device__ __forceinline__ uint4 ld_pkt_if(const uint4* p, int off) {
    uint4 v;
    asm volatile("{.reg .pred p; .reg .b128 x; .reg .b64 l, h, a; setp.ne.u64 p, %4, 0; add.u64 a, %4, %5; mov.b64 l, 0; mov.b128 x, {l, l};\n"
                 "@p ld.relaxed.gpu.global.b128 x, [a]; mov.b128 {l, h}, x; mov.b64 {%0,%1}, l; mov.b64 {%2,%3}, h;}"
                 : "=r"(v.x), "=r"(v.y), "=r"(v.z), "=r"(v.w) : "l"(p), "l"((long long)off) : "memory");
    return v;
}
__device__ __forceinline__ void st_pkt(uint4* p, uint32_t x, uint32_t y, uint32_t z, uint32_t w) {
    asm volatile("{.reg .b128 x; .reg .b64 l, h; mov.b64 l, {%1,%2}; mov.b64 h, {%3,%4}; mov.b128 x, {l, h}; st.relaxed.gpu.global.b128 [%0], x;}"
                 ::"l"(p), "r"(x), "r"(y), "r"(z), "r"(w) : "memory");
}
__device__ __forceinline__ uint32_t lds32(uint32_t a) { uint32_t v; asm volatile("ld.shared.u32 %0, [%1];" : "=r"(v) : "r"(a) : "memory"); return v; }
__device__ __forceinline__ void sts32(uint32_t a, uint32_t v) { asm volatile("st.shared.u32 [%0], %1;" ::"r"(a), "r"(v) : "memory"); }
__device__ __forceinline__ float2 lds64f(uint32_t a) { float2 v; asm volatile("ld.shared.v2.f32 {%0,%1}, [%2];" : "=f"(v.x), "=f"(v.y) : "r"(a) : "memory"); return v; }
__device__ __forceinline__ void sts64f(uint32_t a, float x, float y) { asm volatile("st.shared.v2.f32 [%0], {%1,%2};" ::"r"(a), "f"(x), "f"(y) : "memory"); }
__device__ __forceinline__ float4 lds128f(uint32_t a) {
    float4 v; asm volatile("ld.shared.v4.f32 {%0,%1,%2,%3}, [%4];" : "=f"(v.x), "=f"(v.y), "=f"(v.z), "=f"(v.w) : "r"(a) : "memory"); return v;
}
__device__ __forceinline__ uint4 lds128(uint32_t a) {
    uint4 v; asm volatile("ld.shared.v4.u32 {%0,%1,%2,%3}, [%4];" : "=r"(v.x), "=r"(v.y), "=r"(v.z), "=r"(v.w) : "r"(a) : "memory"); return v;
}
__device__ __forceinline__ uint32_t pack_bf16(float lo, float hi) {
    uint32_t r; asm("cvt.rn.bf16x2.f32 %0, %1, %2;" : "=r"(r) : "f"(hi), "f"(lo)); return r;
}
__device__ __forceinline__ uint32_t mul_bf16x2(uint32_t a, uint32_t b) {
    uint32_t r; asm("mul.rn.bf16x2 %0, %1, %2;" : "=r"(r) : "r"(a), "r"(b)); return r;
}
__device__ __forceinline__ uint32_t fma_bf16x2(uint32_t a, uint32_t b, uint32_t c) {
    uint32_t r; asm("fma.rn.bf16x2 %0, %1, %2, %3;" : "=r"(r) : "r"(a), "r"(b), "r"(c)); return r;
}
__device__ __forceinline__ float ex2f(float x) { float r; asm("ex2.approx.ftz.f32 %0, %1;" : "=f"(r) : "f"(x)); return r; }
__device__ __forceinline__ float rcpf(float x) { float r; asm("rcp.approx.ftz.f32 %0, %1;" : "=f"(r) : "f"(x)); return r; }
__device__ __forceinline__ float bf_lo(uint32_t v) { return __uint_as_float(v << 16); }
__device__ __forceinline__ float bf_hi(uint32_t v) { return __uint_as_float(v & 0xffff0000u); }
__device__ __forceinline__ void stmatrix4(uint32_t a, uint32_t r0, uint32_t r1, uint32_t r2, uint32_t r3) {
    asm volatile("stmatrix.sync.aligned.m8n8.x4.shared.b16 [%0], {%1,%2,%3,%4};" ::"r"(a), "r"(r0), "r"(r1), "r"(r2), "r"(r3) : "memory");
}
__device__ __forceinline__ void stmatrix4_t(uint32_t a, uint32_t r0, uint32_t r1, uint32_t r2, uint32_t r3) {
    asm volatile("stmatrix.sync.aligned.m8n8.x4.trans.shared.b16 [%0], {%1,%2,%3,%4};" ::"r"(a), "r"(r0), "r"(r1), "r"(r2), "r"(r3) : "memory");
}

constexpr uint32_t DK = 1u << 16;
constexpr uint32_t DMN = (PANEL >> 4) << 16;
__device__ __forceinline__ uint64_t desc(uint32_t lo) {
    uint64_t d;
    asm("mov.b64 %0, {%1, %2};" : "=l"(d) : "r"(lo), "r"(0x40000040u));
    return d;
}
__device__ __forceinline__ void wg_fence() { asm volatile("wgmma.fence.sync.aligned;" ::: "memory"); }
__device__ __forceinline__ void wg_commit() { asm volatile("wgmma.commit_group.sync.aligned;" ::: "memory"); }
template <int N> __device__ __forceinline__ void wg_wait() { asm volatile("wgmma.wait_group.sync.aligned %0;" ::"n"(N) : "memory"); }

#define R8(a, o) "+f"(a[o + 0]), "+f"(a[o + 1]), "+f"(a[o + 2]), "+f"(a[o + 3]), "+f"(a[o + 4]), "+f"(a[o + 5]), "+f"(a[o + 6]), "+f"(a[o + 7])
#define L32 "{%0,%1,%2,%3,%4,%5,%6,%7,%8,%9,%10,%11,%12,%13,%14,%15,%16,%17,%18,%19,%20,%21,%22,%23,%24,%25,%26,%27,%28,%29,%30,%31}"
#define L64 "{%0,%1,%2,%3,%4,%5,%6,%7,%8,%9,%10,%11,%12,%13,%14,%15,%16,%17,%18,%19,%20,%21,%22,%23,%24,%25,%26,%27,%28,%29,%30,%31," \
            "%32,%33,%34,%35,%36,%37,%38,%39,%40,%41,%42,%43,%44,%45,%46,%47,%48,%49,%50,%51,%52,%53,%54,%55,%56,%57,%58,%59,%60,%61,%62,%63}"

template <int TA, int ACC>
__device__ __forceinline__ void mma_n64_ss(float (&d)[32], uint64_t da, uint64_t db) {
    asm volatile("wgmma.mma_async.sync.aligned.m64n64k16.f32.bf16.bf16 " L32 ", %32, %33, %35, 1, 1, %34, 0;"
                 : R8(d, 0), R8(d, 8), R8(d, 16), R8(d, 24) : "l"(da), "l"(db), "n"(TA), "n"(ACC));
}
template <int ACC>
__device__ __forceinline__ void mma_n64_rs(float (&d)[32], uint32_t a0, uint32_t a1, uint32_t a2, uint32_t a3, uint64_t db) {
    asm volatile("wgmma.mma_async.sync.aligned.m64n64k16.f32.bf16.bf16 " L32 ", {%32,%33,%34,%35}, %36, %37, 1, 1, 0;"
                 : R8(d, 0), R8(d, 8), R8(d, 16), R8(d, 24) : "r"(a0), "r"(a1), "r"(a2), "r"(a3), "l"(db), "n"(ACC));
}
template <int ACC>
__device__ __forceinline__ void mma_n32_ss(float (&d)[16], uint64_t da, uint64_t db) {
    asm volatile("wgmma.mma_async.sync.aligned.m64n32k16.f32.bf16.bf16 {%0,%1,%2,%3,%4,%5,%6,%7,%8,%9,%10,%11,%12,%13,%14,%15}, %16, %17, %18, 1, 1, 0, 0;"
                 : R8(d, 0), R8(d, 8) : "l"(da), "l"(db), "n"(ACC));
}
__device__ __forceinline__ void mma_n128_tt(float (&d)[64], uint64_t da, uint64_t db) {
    asm volatile("wgmma.mma_async.sync.aligned.m64n128k16.f32.bf16.bf16 " L64 ", %64, %65, 1, 1, 1, 1, 1;"
                 : R8(d, 0), R8(d, 8), R8(d, 16), R8(d, 24), R8(d, 32), R8(d, 40), R8(d, 48), R8(d, 56) : "l"(da), "l"(db));
}

template <int N> __device__ __forceinline__ void pin(uint32_t (&a)[N]) {
#pragma unroll
    for (int i = 0; i < N; i++) asm volatile("" : "+r"(a[i])::"memory");
}
template <int N> __device__ __forceinline__ void pin(float (&a)[N]) {
#pragma unroll
    for (int i = 0; i < N; i++) asm volatile("" : "+f"(a[i])::"memory");
}
__device__ __forceinline__ void scale_state(float (&S)[64], uint32_t vec) {
#pragma unroll
    for (int jj = 0; jj < 8; jj++) {
        float4 p = lds128f(vec + jj * 64);
        S[8 * jj + 0] *= p.x; S[8 * jj + 1] *= p.y; S[8 * jj + 2] *= p.x; S[8 * jj + 3] *= p.y;
        S[8 * jj + 4] *= p.z; S[8 * jj + 5] *= p.w; S[8 * jj + 6] *= p.z; S[8 * jj + 7] *= p.w;
    }
}
constexpr uint32_t SC2 = 0x3D803D80u;
__device__ __forceinline__ void sts128(uint32_t a, uint32_t x, uint32_t y, uint32_t z, uint32_t w) {
    asm volatile("st.shared.v4.u32 [%0], {%1,%2,%3,%4};" ::"r"(a), "r"(x), "r"(y), "r"(z), "r"(w) : "memory");
}
__device__ __forceinline__ void load_vec(float4 (&p)[8], uint32_t vec) {
#pragma unroll
    for (int jj = 0; jj < 8; jj++) p[jj] = lds128f(vec + jj * 64);
}
__device__ __forceinline__ void scale8(float (&S)[64], int jj, const float4& p) {
    S[8 * jj + 0] *= p.x; S[8 * jj + 1] *= p.y; S[8 * jj + 2] *= p.x; S[8 * jj + 3] *= p.y;
    S[8 * jj + 4] *= p.z; S[8 * jj + 5] *= p.w; S[8 * jj + 6] *= p.z; S[8 * jj + 7] *= p.w;
}
__device__ __forceinline__ void cvt_state(const float (&S)[64], uint32_t (&f)[32]) {
#pragma unroll
    for (int i = 0; i < 32; i++) f[i] = pack_bf16(S[2 * i], S[2 * i + 1]);
}

__device__ __forceinline__ uint32_t lds32n(uint32_t a) { uint32_t v; asm volatile("ld.shared.u32 %0, [%1];" : "=r"(v) : "r"(a)); return v; }
__device__ __forceinline__ void sts32n(uint32_t a, uint32_t v) { asm volatile("st.shared.u32 [%0], %1;" ::"r"(a), "r"(v)); }

template <bool FULL, bool FWD>
__device__ __forceinline__ void gate_half(uint32_t tb, float& G0, float& G1) {
    constexpr bool NEEDG = FULL || FWD, NEEDR = FULL || !FWD;
    constexpr int OG = FWD ? ST_K : ST_Q, OR = FWD ? ST_Q : ST_K;
    constexpr int STEP = FWD ? 1024 : -1024;
    uint32_t ad[8];
#pragma unroll
    for (int i = 0; i < 8; i++) ad[i] = (FWD ? tb + 4096 : (tb + 3072) ^ 0x3F0) ^ (i * 0x90);
    constexpr int XN = (!FULL && XDEEP) ? 8 : 4;
    uint32_t gv[4], xg[XN], xr[XN];
    float e0[4], e1[4];
#pragma unroll
    for (int i = 0; i < 4; i++) gv[i] = lds32n(ad[i] + ST_G);
#pragma unroll
    for (int i = 0; i < XN; i++) {
        if (NEEDG) xg[i] = lds32n(ad[i] + OG);
        if (NEEDR) xr[i] = lds32n(ad[i] + OR);
    }
#pragma unroll
    for (int i = 0; i < 4; i++) {
        e0[i] = ex2f(bf_lo(gv[i]) * NLOG2E);
        e1[i] = ex2f(bf_hi(gv[i]) * NLOG2E);
        gv[i] = lds32n(ad[4 + i] + ST_G);
    }
#pragma unroll 1
    for (int b = 0; b < 4; b++) {
#pragma unroll
        for (int h = 0; h < 2; h++) {
            float R0 = 0.f, R1 = 0.f, f0[4], f1[4];
#pragma unroll
            for (int i = 0; i < 4; i++) {
                if (FWD) { G0 = fmaf(G0, e0[i], G0); G1 = fmaf(G1, e1[i], G1); }
                if (NEEDR && i == 3) { R0 = rcpf(G0); R1 = rcpf(G1); }
                if (NEEDG) {
                    sts32n(ad[4 * h + i] + OG, mul_bf16x2(xg[(4 * h + i) % XN], pack_bf16(G0, G1)));
                    xg[(4 * h + i) % XN] = lds32n(XN == 8 ? ad[4 * h + i] + (OG + STEP) : ad[4 * (1 - h) + i] + (OG + h * STEP));
                }
                if (!FWD) { G0 = fmaf(G0, e0[i], G0); G1 = fmaf(G1, e1[i], G1); }
            }
#pragma unroll
            for (int i = 0; i < 4; i++) {
                f0[i] = ex2f(bf_lo(gv[i]) * NLOG2E);
                f1[i] = ex2f(bf_hi(gv[i]) * NLOG2E);
                gv[i] = lds32n(ad[4 * h + i] + (ST_G + STEP));
            }
            if (NEEDR) {
#pragma unroll
                for (int i = 3; i >= 0; i--) {
                    if (!FWD && i < 3) { R0 = fmaf(R0, e0[i], R0); R1 = fmaf(R1, e1[i], R1); }
                    sts32n(ad[4 * h + i] + OR, mul_bf16x2(xr[(4 * h + i) % XN], pack_bf16(R0, R1)));
                    xr[(4 * h + i) % XN] = lds32n(XN == 8 ? ad[4 * h + i] + (OR + STEP) : ad[4 * (1 - h) + i] + (OR + h * STEP));
                    if (FWD && i > 0) { R0 = fmaf(R0, e0[i], R0); R1 = fmaf(R1, e1[i], R1); }
                }
            }
#pragma unroll
            for (int i = 0; i < 4; i++) { e0[i] = f0[i]; e1[i] = f1[i]; }
        }
#pragma unroll
        for (int i = 0; i < 8; i++) ad[i] += (uint32_t)STEP;
    }
}

#define GD 2
#define XD 2
template <bool FWD>
__device__ __forceinline__ void gate_state(uint32_t tb, float& G0, float& G1) {
    constexpr bool NEEDG = FWD, NEEDR = !FWD;
    constexpr int OG = FWD ? ST_K : ST_Q, OR = FWD ? ST_Q : ST_K;
    constexpr int STEP = FWD ? 1024 : -1024;
    constexpr int XDD = XD;
    uint32_t ad[8];
#pragma unroll
    for (int i = 0; i < 8; i++) ad[i] = (FWD ? tb + 4096 : (tb + 3072) ^ 0x3F0) ^ (i * 0x90);
    auto row = [&](int r, int off) { return ad[r & 7] + (uint32_t)((r >> 3) * STEP + off); };
    uint32_t gv[32], xg[32], xr[32];
    float e0[32], e1[32];
#pragma unroll
    for (int r = 0; r < 4 * (GD + 1); r++) gv[r] = lds32n(row(r, ST_G));
#pragma unroll
    for (int r = 0; r < 4 * XDD; r++) {
        if (NEEDG) xg[r] = lds32n(row(r, OG));
        if (NEEDR) xr[r] = lds32n(row(r, OR));
    }
#pragma unroll
    for (int r = 0; r < 4; r++) {
        e0[r] = ex2f(bf_lo(gv[r]) * NLOG2E);
        e1[r] = ex2f(bf_hi(gv[r]) * NLOG2E);
    }
#pragma unroll
    for (int j = 0; j < 32; j += 4) {
        float R0 = 0.f, R1 = 0.f;
#pragma unroll
        for (int r = j; r < j + 4; r++) {
            if (FWD) { G0 = fmaf(G0, e0[r], G0); G1 = fmaf(G1, e1[r], G1); }
            if (NEEDR && r == j + 3) { R0 = rcpf(G0); R1 = rcpf(G1); }
            if (NEEDG) {
                sts32n(row(r, OG), mul_bf16x2(xg[r], pack_bf16(G0, G1)));
                if (r + 4 * XDD < 32) xg[r + 4 * XDD] = lds32n(row(r + 4 * XDD, OG));
            }
            if (!FWD) { G0 = fmaf(G0, e0[r], G0); G1 = fmaf(G1, e1[r], G1); }
        }
#pragma unroll
        for (int r = j + 4; r < j + 8; r++) {
            if (r < 32) {
                e0[r] = ex2f(bf_lo(gv[r]) * NLOG2E);
                e1[r] = ex2f(bf_hi(gv[r]) * NLOG2E);
            }
            if (r + 4 * GD < 32) gv[r + 4 * GD] = lds32n(row(r + 4 * GD, ST_G));
        }
        if (NEEDR) {
#pragma unroll
            for (int r = j + 3; r >= j; r--) {
                if (!FWD && r < j + 3) { R0 = fmaf(R0, e0[r], R0); R1 = fmaf(R1, e1[r], R1); }
                sts32n(row(r, OR), mul_bf16x2(xr[r], pack_bf16(R0, R1)));
                if (r + 4 * XDD < 32) xr[r + 4 * XDD] = lds32n(row(r + 4 * XDD, OR));
                if (FWD && r > j) { R0 = fmaf(R0, e0[r], R0); R1 = fmaf(R1, e1[r], R1); }
            }
        }
    }
}

struct Ring {
    int s, ph;
    __device__ __forceinline__ Ring() : s(0), ph(0) {}
    template <int N> __device__ __forceinline__ void next() { if (++s == N) { s = 0; ph ^= 1; } }
};

__device__ __forceinline__ float fallback_chunk(const __nv_bfloat16* __restrict__ q, const __nv_bfloat16* __restrict__ k,
                                             const __nv_bfloat16* __restrict__ g, size_t goff, uint32_t st, int t, int full,
                                             float* __restrict__ fb) {
    const int panel = t >> 6, cc = t & 63;
    auto saddr = [&](int row) { return (uint32_t)(panel * PANEL + row * 128 + ((((cc >> 3) ^ (row & 7)) << 4) | ((cc & 7) << 1))); };
    float P = 1.f;
    for (int r = 0; r < CH; r++) {
        float gv = __bfloat162float(g[goff + (size_t)r * D_ + t]);
        float a = 1.f / (1.f + __expf(-gv));
        fb[r * 128 + t] = a;
        P *= a;
        if (full) {
            __nv_bfloat16 o = __float2bfloat16(__bfloat162float(q[goff + (size_t)r * D_ + t]) * P);
            asm volatile("st.shared.u16 [%0], %1;" ::"r"(st + ST_Q + saddr(r)), "h"(__bfloat16_as_ushort(o)) : "memory");
        }
    }
    float R = 1.f;
    for (int r = CH - 1; r >= 0; r--) {
        __nv_bfloat16 o = __float2bfloat16(__bfloat162float(k[goff + (size_t)r * D_ + t]) * R);
        asm volatile("st.shared.u16 [%0], %1;" ::"r"(st + ST_K + saddr(r)), "h"(__bfloat16_as_ushort(o)) : "memory");
        R *= fb[r * 128 + t];
    }
    if (full) {
        for (int i = t; i < CH * CH; i += 128) sts32(st + ST_G + i * 4, 0u);
        __threadfence_block();
        bar_sync128<2>();
        const int j = t & 63, dh = t >> 6;
        for (int db = 0; db < 16; db++) {
            const int d0 = dh * 64 + db * 4;
            float p[4];
#pragma unroll
            for (int u = 0; u < 4; u++) p[u] = __bfloat162float(k[goff + (size_t)j * D_ + d0 + u]);
            for (int i = j; i < CH; i++) {
                float s = 0.f;
#pragma unroll
                for (int u = 0; u < 4; u++) {
                    if (i > j) p[u] *= fb[i * 128 + d0 + u];
                    s += __bfloat162float(q[goff + (size_t)i * D_ + d0 + u]) * p[u];
                }
                asm volatile("red.shared.add.f32 [%0], %1;" ::"r"(st + ST_G + (i * CH + j) * 4), "f"(s) : "memory");
            }
        }
        bar_sync128<2>();
        uint32_t pk[16];
        const int row = t >> 1, c0 = (t & 1) * 32;
#pragma unroll
        for (int u = 0; u < 16; u++) {
            float2 v = lds64f(st + ST_G + (row * CH + c0 + 2 * u) * 4);
            pk[u] = pack_bf16(v.x, v.y);
        }
        bar_sync128<2>();
#pragma unroll
        for (int u = 0; u < 16; u++) {
            const int c = c0 + 2 * u;
            sts32(st + ST_A + row * 128 + ((((c >> 3) ^ (row & 7)) << 4) | ((c & 7) << 1)), pk[u]);
        }
    } else {
        bar_sync128<2>();
    }
    return P;
}

__global__ void __cluster_dims__(2, 1, 1) __launch_bounds__(384, 1)
gla_kernel(const __grid_constant__ CUtensorMap tm_q, const __grid_constant__ CUtensorMap tm_k,
           const __grid_constant__ CUtensorMap tm_g, const __grid_constant__ CUtensorMap tm_v,
           const __grid_constant__ CUtensorMap tm_o, const __grid_constant__ Sched sched,
           const __nv_bfloat16* __restrict__ gq, const __nv_bfloat16* __restrict__ gk, const __nv_bfloat16* __restrict__ gg,
           const __nv_bfloat16* __restrict__ gv, uint4* p_state, unsigned int* p_epoch, float* p_fb) {
    extern __shared__ __align__(1024) uint8_t smem_raw[];
    TRACE_GT(0);
    uint32_t sm = smem_u32(smem_raw);
    if ((sm & 0xFFFFFFu) != SM_BASE) __trap();
    asm volatile("" : "+r"(sm));
    const int tid = threadIdx.x, lane = tid & 31;
    const int warp = __shfl_sync(0xffffffffu, tid >> 5, 0), wg = warp >> 2;
    uint32_t rank;
    asm volatile("mov.u32 %0, %%cluster_ctarank;" : "=r"(rank));
    const int cid = blockIdx.x >> 1;
    const int head = cid >> 2, pair = cid & 7;
    const uint32_t bars = sm + OFF_BAR;
    auto BAR = [&](int i) { return bars + 8 * i; };
    const int nseg = sched.nseg[pair];

    const int8_t* seq = sched.seq[pair];
    auto load_stage = [&](int n, int s) {
        const int e = seq[n];
        if (e < 0) return;
        const int row = head * T_ + (e & 63) * CH;
        const uint32_t st = sm + OFF_ST + s * ST_BYTES, fb = BAR(B_FULL + s);
        mbar_expect_tx(fb, (e & 64) ? 6 * PANEL : 4 * PANEL);
        const uint64_t pol = ((HINT & 1) && (e & 64)) ? L2_FIRST : L2_NORMAL;
        tma_load3(st + ST_G, &tm_g, fb, 0, row, 2 * rank, pol);
        tma_load3(st + ST_K, &tm_k, fb, 0, row, 2 * rank, pol);
        if (e & 64) tma_load3(st + ST_Q, &tm_q, fb, 0, row, 2 * rank, pol);
    };
    auto load_v = [&](int n, int j, int piece) {
        const int e = seq[n];
        if (e < 0) return;
        const int pn = 2 * (piece ? (int)rank : 1 - (int)rank) + j;
        const uint32_t fb = BAR(B_VFULL + j * 4 + (pn & 2) + (n & 1)), dst = sm + OFF_V + (n & 1) * V_BYTES + pn * PANEL;
        const uint64_t pol = ((HINT & 4) && (e & 64) && piece) ? L2_FIRST : L2_NORMAL;
        mbar_expect_tx(fb, PANEL);
        if (!MC || n < 2) tma_load3(dst, &tm_v, fb, 0, head * T_ + (e & 63) * CH, pn, pol);
        else if (piece) tma_load3_both(dst, &tm_v, fb, 0, head * T_ + (e & 63) * CH, pn, pol);
    };

    auto init_rest = [&]() {
        for (int i = 0; i < NST; i++) {
            if (i) mbar_init(BAR(B_FULL + i), 1);
            mbar_init(BAR(B_QK + i), 4);
            mbar_init(BAR(B_A + i), 4);
            sts32(BAR(B_EMPTY + i), 0u);
        }
        for (int i = 0; i < 8; i++) { mbar_init(BAR(B_VFULL + i), 1); mbar_init(BAR(B_VFREE + i), 4); }
        for (int i = 0; i < 2; i++) {
            mbar_init(BAR(B_INFULL + i), 1);
            mbar_init(BAR(B_INFREE + i), 1);
            mbar_expect_tx(BAR(B_INFULL + i), PANEL);
        }
        for (int i = 0; i < 4; i++) mbar_init(BAR(B_PFREE + i), 1);
        mbar_init(BAR(B_TAG + 1), 1);
    };
    if (tid == 0) {
        mbar_init(BAR(B_FULL), 1);
        if (!(PRO & 1)) init_rest();
        asm volatile("fence.mbarrier_init.release.cluster;" ::: "memory");
        fence_async();
        load_stage(0, 0);
    } else if ((PRO & 1) && tid == 32) {
        init_rest();
        asm volatile("fence.mbarrier_init.release.cluster;" ::: "memory");
        fence_async();
    } else if ((PRO & 2) && tid == 96) {
        asm volatile("prefetch.tensormap [%0];" ::"l"(&tm_v) : "memory");
        asm volatile("prefetch.tensormap [%0];" ::"l"(&tm_o) : "memory");
    }
    __syncthreads();
    asm volatile("barrier.cluster.arrive.relaxed.aligned;" ::: "memory");

    if (wg == 2) {
        asm volatile("setmaxnreg.dec.sync.aligned.u32 56;");
        TRACE_DECL(2)
        TRACE(0);
        const int t = tid - 256, w = warp & 3;
        const int half = w >> 1, panel = w & 1;
        Ring rs;
        int fpar = 0, spar = 0;
        float2 fnext = make_float2(1.f, 1.f);
        float D0 = 1.f, D1 = 1.f;
        for (int si = -(DRY & 3); si < nseg; si++) {
            Seg sg = sched.seg[pair][si < 0 ? 0 : si];
            if (si < 0) { sg.full ^= (si & 1) ^ 1; sg.c0 = 0; sg.c1 = 1; rs.s = NST - 1; rs.ph = 1; }
            bool fpend = sg.full && sg.c0 > 0;
            D0 = 1.f; D1 = 1.f;
            for (int c = sg.c0; c < sg.c1; c++) {
                const uint32_t st = sm + OFF_ST + rs.s * ST_BYTES;
                mbar_wait(BAR(B_FULL + rs.s), rs.ph);
                TRACE(1);
                const uint32_t tb = st + panel * PANEL + lane * 4;
                float G0 = 1.f, G1 = 1.f;
                if (sg.full) {
                    if (half) gate_half<true, true>(tb, G0, G1); else gate_half<true, false>(tb, G0, G1);
                } else {
                    if (GD == 0) { if (half) gate_half<false, true>(tb, G0, G1); else gate_half<false, false>(tb, G0, G1); }
                    else if (half) gate_state<true>(tb, G0, G1); else gate_state<false>(tb, G0, G1);
                }
                if (si < 0) { rs.next<NST>(); continue; }
                const bool bad = !(G0 <= G_LIMIT && G1 <= G_LIMIT);
                const int cp = panel * 32 + (opaque_tid() & 31);
                const uint32_t voff = (cp >> 3) * 64 + (cp & 3) * 16 + ((cp >> 2) & 1) * 8;
                const float r0 = rcpf(G0), r1 = rcpf(G1);
                if (half) sts64f(sm + OFF_FBUF + fpar * 512 + voff, r0, r1);
                const float2 fprev = fpend ? fnext : make_float2(1.f, 1.f);
                fence_async();
                TRACE(2);
                const bool anybad = bar_red_or1(bad);
                TRACE(3);
                const uint32_t vec = st + ST_VEC;
                if (__builtin_expect(!anybad, 1)) {
                    if (!half) {
                        const float p0 = fprev.x * r0, p1 = fprev.y * r1;
                        if (fpend) { D0 *= p0; D1 *= p1; }
                        sts64f(vec + VEC_P1 + voff, p0, p1);
                        if (!sg.full && c + 1 == sg.c1) sts64f(sm + OFF_PD + spar * 512 + voff, D0, D1);
                        if (t == 0) sts32(vec + VEC_FLAG, 0u);
                    }
                    __syncwarp();
                    if (elect_one()) {
                        mbar_arrive(BAR(B_QK + rs.s));
                        if (!sg.full) mbar_arrive(BAR(B_A + rs.s));
                    }
                    fnext = lds64f(sm + OFF_FBUF + fpar * 512 + voff);
                } else {
                    const int t = opaque_tid() - 256;
                    const size_t goff = ((size_t)head * T_ + (size_t)c * CH) * D_ + rank * 128;
                    const float P = fallback_chunk(gq, gk, gg, goff, st, t, sg.full, p_fb + (size_t)blockIdx.x * CH * 128);
                    const uint32_t vo = (t >> 4) * 64 + ((t >> 1) & 3) * 16 + ((t >> 3) & 1) * 8 + (t & 1) * 4;
                    sts32(vec + VEC_P2 + vo, __float_as_uint(P));
                    fnext = make_float2(1.f, 1.f);
                    bar_sync128<2>();
                    if (!half) {
                        const float2 pp = lds64f(vec + VEC_P2 + voff);
                        D0 *= fprev.x * pp.x; D1 *= fprev.y * pp.y;
                        sts64f(vec + VEC_P1 + voff, fprev.x, fprev.y);
                        if (!sg.full && c + 1 == sg.c1) sts64f(sm + OFF_PD + spar * 512 + voff, D0, D1);
                        if (t == 0) sts32(vec + VEC_FLAG, 1u);
                    }
                    fence_async();
                    __syncwarp();
                    if (elect_one()) { mbar_arrive(BAR(B_QK + rs.s)); mbar_arrive(BAR(B_A + rs.s)); }
                }
                TRACE(5);
                fpar ^= 1;
                fpend = true;
                rs.next<NST>();
            }
            if (!sg.full && si >= 0) spar ^= 1;
        }
        asm volatile("barrier.cluster.wait.acquire.aligned;" ::: "memory");
        asm volatile("barrier.cluster.arrive.relaxed.aligned;" ::: "memory");
        asm volatile("barrier.cluster.wait.acquire.aligned;" ::: "memory");
    } else {
        asm volatile("setmaxnreg.inc.sync.aligned.u32 224;");
        TRACE_DECL(wg)
        TRACE(0);
        const int t = tid & 127, w = warp & 3;
        const int ps = 2 * (1 - (int)rank) + wg, pk = 2 * (int)rank + wg;
        const uint32_t vq = (lane & 3) * 16;
        const uint32_t o_off = ((lane & 7) + ((lane >> 4) << 3)) * 128 + (((2 * w + ((lane >> 3) & 1)) ^ (lane & 7)) << 4);
        const uint32_t inbox = sm + OFF_INBOX + wg * PANEL;
        constexpr uint32_t dst0 = (SM_BASE + OFF_ST) >> 4, dv0 = DMN + ((SM_BASE + OFF_V) >> 4);
        const uint32_t vfull = BAR(B_VFULL + wg * 4 + 2 - 2 * (int)rank), vfree = BAR(B_VFREE + wg * 4);

        float S0[64], S1[64];
        Ring rs, rv;
        int xph = 0;
        bool synced = false;
        int spar = 0;

        auto mma_kv = [&](float (&S)[64], int piece) {
            const uint32_t dk = dst0 + DMN + (ST_K >> 4) + rs.s * (ST_BYTES >> 4);
            const uint32_t dv = dv0 + rv.s * (V_BYTES >> 4) + piece * (PANEL >> 4);
#pragma unroll
            for (int ks = 0; ks < 4; ks++) mma_n128_tt(S, desc(dv + ks * 128), desc(dk + ks * 128));
        };
        auto prev_stage = [&]() { return (rs.s == 0) ? NST - 1 : rs.s - 1; };
        int n = 0;
        if (SDELAY == 1 && warp == 3) mbar_wait(BAR(B_FULL), 0);
        if (SDELAY > 1 && warp == 3) __nanosleep(SDELAY);
        if (warp == 3 && elect_one()) {
            load_v(0, 0, 0); load_v(0, 1, 0); load_v(0, 0, 1); load_v(0, 1, 1);
            load_stage(1, 1);
            if (OPT & 4) { load_v(1, 0, 0); load_v(1, 1, 0); load_v(1, 0, 1); load_v(1, 1, 1); }
        }
        if (warp == 7 && elect_one()) {
            uint32_t v;
            asm volatile("ld.relaxed.gpu.global.u32 %0, [%1];" : "=r"(v) : "l"(p_epoch + blockIdx.x) : "memory");
            sts32(BAR(B_TAG), v);
            mbar_arrive(BAR(B_TAG + 1));
        }
        __syncwarp();
        auto get_tag = [&]() { mbar_wait(BAR(B_TAG + 1), 0); return lds32(BAR(B_TAG)); };
        auto late_init = [&]() {
            if (!(OPT & 4) && warp == 5 && elect_one()) { load_v(1, 0, 0); load_v(1, 1, 0); load_v(1, 0, 1); load_v(1, 1, 1); }
            if (warp == 6 && elect_one()) load_stage(2, 2);
            __syncwarp();
        };
        auto refill_stage = [&](uint32_t bar, uint32_t ph) {
            if (w == 2) {
                mbar_wait(bar, ph);
                if (elect_one()) {
                    uint32_t old;
                    asm volatile("atom.relaxed.cta.shared.add.u32 %0, [%1], 1;" : "=r"(old) : "r"(BAR(B_EMPTY + prev_stage())) : "memory");
                    if (old & 1) load_stage(n + 2, prev_stage());
                }
                __syncwarp();
            }
        };
        auto prefetch = [&](int m) {
            if (PFD > 0 && w == 3 && elect_one()) {
                const int e = seq[m];
                if (e >= 0) {
                    const size_t off = ((size_t)head * T_ + (e & 63) * CH + rank * (CH / 2)) * D_;
                    if (wg) { l2_prefetch(gg + off); l2_prefetch(gv + off); }
                    else { l2_prefetch(gk + off); if (e & 64) l2_prefetch(gq + off); }
                }
            }
            __syncwarp();
        };

        for (int si = 0; si < nseg; si++) {
            const Seg sg = sched.seg[pair][si];
            if (!sg.full || sg.c0 == 0) {
#pragma unroll
                for (int i = 0; i < 64; i++) { S0[i] = 0.f; S1[i] = 0.f; }
            }
            if (!sg.full) {
                const uint4* src = p_state + (size_t)(((head * NSLOT + (sg.comb & 15)) * 2 + rank) * 2 + wg) * 2048 + t;
                auto issue = [&]() {
                    const uint32_t st = sm + OFF_ST + rs.s * ST_BYTES;
                    wg_wait<0>();
                    mbar_wait2(vfull + rv.s * 8, rv.ph, (vfull ^ 16) + rv.s * 8, rv.ph);
                    mbar_wait(BAR(B_QK + rs.s), rs.ph);
                    TRACE(10);
                    const uint32_t flag = lds32(st + ST_VEC + VEC_FLAG);
                    float4 p[8];
                    load_vec(p, st + ST_VEC + VEC_P1 + vq);
                    const bool p2 = __any_sync(0xffffffffu, flag != 0);
#pragma unroll
                    for (int jj = 0; jj < 8; jj++) scale8(S0, jj, p[jj]);
                    if (__builtin_expect(p2, 0)) scale_state(S0, st + ST_VEC + VEC_P2 + vq);
                    TRACE(11);
                    pin(S0);
                    wg_fence();
                    mma_kv(S0, ps);
#pragma unroll
                    for (int jj = 0; jj < 8; jj++) scale8(S1, jj, p[jj]);
                    if (__builtin_expect(p2, 0)) scale_state(S1, st + ST_VEC + VEC_P2 + vq);
                    pin(S1);
                    wg_fence();
                    mma_kv(S1, pk);
                    wg_commit();
                    if (n == 0) late_init();
                    if (MC && !synced) { asm volatile("barrier.cluster.wait.acquire.aligned;" ::: "memory"); synced = true; }
                };
                auto finish = [&]() {
                    wg_wait<0>();
                    pin(S0); pin(S1);
                    TRACE(12);
                    if (elect_one()) {
                        mbar_arrive(vfree + rv.s * 8);
                        mbar_arrive(vfree + 16 + rv.s * 8);
                    }
                    if (w == 1) {
                        mbar_wait(vfree + 16 + rv.s * 8, rv.ph);
                        if (MC) {
                            const uint32_t pf = BAR(B_PFREE + wg * 2 + rv.s);
                            if (elect_one()) mbar_arrive_remote(mapa(pf, rank ^ 1));
                            __syncwarp();
                            mbar_wait(pf, (spar >> (1 + rv.s)) & 1);
                            fence_acq_cluster();
                        }
                        if (elect_one()) { load_v(n + 2, wg, 0); load_v(n + 2, wg, 1); }
                        __syncwarp();
                    }
                    spar ^= 2 << rv.s;
                    prefetch(n + 2 + PFD);
                    rs.next<NST>(); rv.next<NVS>(); n++;
                    refill_stage(vfree + 16 + (rv.s ^ 1) * 8, rv.s == 0 ? rv.ph ^ 1 : rv.ph);
                };
                for (int c = sg.c0 + 1; c < sg.c1; c++) { issue(); finish(); }
                uint4 pkt[16];
                const bool comb = sg.comb < 16;
                if (!PROBE) pkt[15] = ld_pkt_if(comb ? src : nullptr, 15 * 2048);
                issue();
                if (PROBE) pkt[15] = ld_pkt_if(comb ? src : nullptr, 15 * 2048);
                const uint32_t ptag = get_tag();
                if (PROBE == 4) finish();
                if (!comb) pkt[15].x = ptag;
                const uint4* src1 = __all_sync(0xffffffffu, (pkt[15].x ^ ptag) & 1) ? src : nullptr;
#pragma unroll
                for (int i = 0; i < 15; i++) pkt[i] = ld_pkt_if(src1, i * 2048);
                if (PROBE != 4) finish();
                TRACE(30);
                if (comb) {
                    const uint32_t vec = sm + OFF_PD + (spar & 1) * 512 + vq;
                    int it = 0;
                    for (;;) {
                        uint32_t ok = 1;
#pragma unroll
                        for (int i = 0; i < 16; i++) ok &= pkt[i].x ^ ptag;
                        if (__all_sync(0xffffffffu, ok & 1)) break;
                        for (;;) {
                            pkt[15] = ld_pkt(src + 15 * 128);
                            if (__all_sync(0xffffffffu, (pkt[15].x ^ ptag) & 1)) break;
                            __nanosleep(PSLEEP);
                            spin_check(++it);
                        }
#pragma unroll
                        for (int i = 0; i < 15; i++) pkt[i] = ld_pkt(src + i * 128);
                        spin_check(++it);
                    }
                    TRACE(31);
#pragma unroll
                    for (int jj = 0; jj < 8; jj++) {
                        const uint4 a = pkt[jj], b = pkt[8 + jj];
                        const float4 p = lds128f(vec + jj * 64);
                        S0[8 * jj + 0] = fmaf(bf_lo(a.x), p.x, S0[8 * jj + 0]); S0[8 * jj + 1] = fmaf(bf_hi(a.x), p.y, S0[8 * jj + 1]);
                        S0[8 * jj + 2] = fmaf(bf_lo(a.y), p.x, S0[8 * jj + 2]); S0[8 * jj + 3] = fmaf(bf_hi(a.y), p.y, S0[8 * jj + 3]);
                        S0[8 * jj + 4] = fmaf(bf_lo(a.z), p.z, S0[8 * jj + 4]); S0[8 * jj + 5] = fmaf(bf_hi(a.z), p.w, S0[8 * jj + 5]);
                        S0[8 * jj + 6] = fmaf(bf_lo(a.w), p.z, S0[8 * jj + 6]); S0[8 * jj + 7] = fmaf(bf_hi(a.w), p.w, S0[8 * jj + 7]);
                        S1[8 * jj + 0] = fmaf(bf_lo(b.x), p.x, S1[8 * jj + 0]); S1[8 * jj + 1] = fmaf(bf_hi(b.x), p.y, S1[8 * jj + 1]);
                        S1[8 * jj + 2] = fmaf(bf_lo(b.y), p.x, S1[8 * jj + 2]); S1[8 * jj + 3] = fmaf(bf_hi(b.y), p.y, S1[8 * jj + 3]);
                        S1[8 * jj + 4] = fmaf(bf_lo(b.z), p.z, S1[8 * jj + 4]); S1[8 * jj + 5] = fmaf(bf_hi(b.z), p.w, S1[8 * jj + 5]);
                        S1[8 * jj + 6] = fmaf(bf_lo(b.w), p.z, S1[8 * jj + 6]); S1[8 * jj + 7] = fmaf(bf_hi(b.w), p.w, S1[8 * jj + 7]);
                    }
                    TRACE(32);
                }
                spar ^= 1;
            } else {
                if (!synced) { asm volatile("barrier.cluster.wait.acquire.aligned;" ::: "memory"); synced = true; }
                float o[32];
                uint32_t fr[32];
#pragma unroll
                for (int i = 0; i < 32; i++) o[i] = 0.f;
                auto mma_qs = [&]() {
                    const uint32_t dq = dst0 + DK + (ST_Q >> 4) + rs.s * (ST_BYTES >> 4);
#pragma unroll
                    for (int ks = 0; ks < 8; ks++) {
                        const uint64_t db = desc(dq + (ks >> 2) * (PANEL >> 4) + (ks & 3) * 2);
                        if (ks == 0) mma_n64_rs<0>(o, fr[0], fr[1], fr[2], fr[3], db);
                        else mma_n64_rs<1>(o, fr[4 * ks], fr[4 * ks + 1], fr[4 * ks + 2], fr[4 * ks + 3], db);
                    }
                };
                auto mma_av = [&](int piece) {
                    const uint32_t da = dst0 + DK + (ST_A >> 4) + rs.s * (ST_BYTES >> 4);
                    const uint32_t dv = dv0 + rv.s * (V_BYTES >> 4) + piece * (PANEL >> 4);
#pragma unroll
                    for (int ks = 0; ks < 4; ks++) mma_n64_ss<1, 1>(o, desc(dv + ks * 128), desc(da + ks * 2));
                };
                const int dj = (w == 0);
                auto duty_top = [&](int c, bool refill) {
                    const uint32_t ph = rv.s == 0 ? rv.ph ^ 1 : rv.ph, vf = BAR(B_VFREE + 2 + (rv.s ^ 1));
                    if (w == 0 || w == 3) {
                        mbar_wait(vf + dj * 32, ph);
                        if (elect_one()) {
                            const int pn = 2 * (int)rank + dj;
                            tma_store3(&tm_o, sm + OFF_V + (rv.s ^ 1) * V_BYTES + pn * PANEL, 0, head * T_ + c * CH, pn);
                            asm volatile("cp.async.bulk.commit_group;" ::: "memory");
                            mbar_expect_tx(BAR(B_INFULL + dj), PANEL);
                            mbar_arrive_remote(mapa(BAR(B_INFREE + dj), rank ^ 1));
                        }
                    } else if (w == 2 && refill) {
                        mbar_wait2(vf, ph, vf + 32, ph);
                        if (elect_one()) load_stage(n + 2, prev_stage());
                    }
                    __syncwarp();
                };
                auto refill_keep = [&]() {
                    if ((w == 0 || w == 3) && elect_one()) {
                        asm volatile("cp.async.bulk.wait_group.read 0;" ::: "memory");
                        load_v(n + 1, dj, 1);
                    }
                    __syncwarp();
                };
                auto refill_send = [&]() {
                    if (w == 1) {
                        if (!MC) mbar_wait2(BAR(B_INFREE), xph ^ 1, BAR(B_INFREE + 1), xph ^ 1);
                        if (elect_one()) { load_v(n + 1, 0, 0); load_v(n + 1, 1, 0); }
                        __syncwarp();
                    }
                };
                auto staged = [&]() {
                    fence_async();
                    __syncwarp();
                    if (elect_one()) mbar_arrive(vfree + 16 + (rv.s ^ 1) * 8);
                };
                mbar_wait2(BAR(B_QK + rs.s), rs.ph, vfull + rv.s * 8, rv.ph);
                uint32_t flag = lds32(sm + OFF_ST + rs.s * ST_BYTES + ST_VEC + VEC_FLAG);
                float4 p[8];
                load_vec(p, sm + OFF_ST + rs.s * ST_BYTES + ST_VEC + VEC_P1 + vq);
                uint4 pi[4];
#pragma unroll
                for (int i = 0; i < 4; i++) pi[i] = make_uint4(0u, 0u, 0u, 0u);
                auto publish = [&](int c) {
                    const int slot = sched.pub[head & 1][c];
                    if (__builtin_expect(slot >= 0, 0)) {
                        const uint32_t ptag = get_tag();
                        uint4* dst = p_state + (size_t)(((head * NSLOT + slot) * 2 + rank) * 2 + wg) * 2048 + (opaque_tid() & 127);
#pragma unroll
                        for (int jj = 0; jj < 8; jj++) {
                            scale8(S0, jj, p[jj]); scale8(S1, jj, p[jj]);
                            p[jj] = make_float4(1.f, 1.f, 1.f, 1.f);
                            st_pkt(dst + jj * 128, (pack_bf16(S0[8 * jj], S0[8 * jj + 1]) | 1u) ^ ptag, pack_bf16(S0[8 * jj + 2], S0[8 * jj + 3]),
                                   pack_bf16(S0[8 * jj + 4], S0[8 * jj + 5]), pack_bf16(S0[8 * jj + 6], S0[8 * jj + 7]));
                            st_pkt(dst + (8 + jj) * 128, (pack_bf16(S1[8 * jj], S1[8 * jj + 1]) | 1u) ^ ptag, pack_bf16(S1[8 * jj + 2], S1[8 * jj + 3]),
                                   pack_bf16(S1[8 * jj + 4], S1[8 * jj + 5]), pack_bf16(S1[8 * jj + 6], S1[8 * jj + 7]));
                        }
                        TRACE(33);
                    }
                };
                auto stage_o = [&]() {
                    const uint32_t stg = sm + OFF_V + (rv.s ^ 1) * V_BYTES + pk * PANEL + o_off;
#pragma unroll
                    for (int i = 0; i < 4; i++) stmatrix4_t(stg + i * 2048, pi[i].x, pi[i].y, pi[i].z, pi[i].w);
                };
                for (int c = sg.c0; c < sg.c1; c++) {
                    const uint32_t st = sm + OFF_ST + rs.s * ST_BYTES;
                    wg_wait<0>();
                    publish(c);
                    if (wg == 0) {
                        const uint32_t dq = dst0 + DK + rs.s * (ST_BYTES >> 4);
                        pin(o);
                        wg_fence();
#pragma unroll
                        for (int ks = 0; ks < 8; ks++) {
                            const uint32_t of = (ks >> 2) * (PANEL >> 4) + (ks & 3) * 2;
                            if (ks == 0) mma_n64_ss<0, 0>(o, desc(dq + (ST_Q >> 4) + of), desc(dq + (ST_K >> 4) + of));
                            else mma_n64_ss<0, 1>(o, desc(dq + (ST_Q >> 4) + of), desc(dq + (ST_K >> 4) + of));
                        }
                        wg_commit();
                    }
                    TRACE(20);
                    pin(S0); pin(S1);
                    if (c > sg.c0) stage_o();
#pragma unroll
                    for (int jj = 0; jj < 8; jj++) {
                        scale8(S0, jj, p[jj]); scale8(S1, jj, p[jj]);
#pragma unroll
                        for (int i = 0; i < 4; i++) fr[4 * jj + i] = pack_bf16(S0[8 * jj + 2 * i], S0[8 * jj + 2 * i + 1]);
                    }
                    const bool p2 = __any_sync(0xffffffffu, flag != 0);
                    if (__builtin_expect(p2, 0)) scale_state(S0, st + ST_VEC + VEC_P2 + vq);
                    if (wg == 1) {
                        if (c > sg.c0) { staged(); duty_top(c - 1, true); }
                        if (n == 0) late_init();
                        if (STAGGER) mbar_wait(BAR(B_A + rs.s), rs.ph);
                    }
                    TRACE(23);
                    pin(S0); pin(fr); pin(S1);
                    wg_fence();
                    mma_kv(S0, ps);
                    wg_commit();
                    TRACE(29);
                    const int ln = opaque_tid() & 31;
                    int di = w * 16 + (ln >> 2) - (ln & 3) * 2;
                    uint32_t sa = st + ST_A + (w * 16 + (ln & 15)) * 128 + (((ln >> 4) ^ (ln & 7)) << 4);
                    asm volatile("" : "+r"(di), "+r"(sa));
                    wg_wait<1>();
                    pin(o);
                    if (wg == 0) {
                        TRACE(27);
                        if (!p2) {
#pragma unroll
                            for (int jb = 0; jb < 4; jb++) {
                                uint32_t r[4];
#pragma unroll
                                for (int x = 0; x < 4; x++) {
                                    const int dj = jb * 16 + (x >> 1) * 8 - (x & 1) * 8;
                                    const float lo = (dj <= di) ? o[8 * jb + 2 * x] : 0.f;
                                    const float hi = (dj + 1 <= di) ? o[8 * jb + 2 * x + 1] : 0.f;
                                    r[x] = pack_bf16(lo, hi);
                                }
                                stmatrix4(sa ^ (jb << 5), r[0], r[1], r[2], r[3]);
                            }
                        }
                    }
                    auto a_done = [&]() {
                        if (wg == 0) {
                            fence_async();
                            __syncwarp();
                            if (elect_one()) {
                                if (!p2) mbar_arrive(BAR(B_A + rs.s));
                                if (c > sg.c0) mbar_arrive(vfree + 16 + (rv.s ^ 1) * 8);
                            }
                        }
                    };
                    if (!(OPT & 2)) a_done();
                    TRACE(18);
                    pin(o); pin(fr);
                    wg_fence();
                    mma_qs();
                    if (OPT & 2) a_done();
                    mbar_wait(BAR(B_A + rs.s), rs.ph);
                    wg_fence();
                    mma_av(ps);
                    wg_commit();
                    TRACE(28);
                    if (wg == 1 && c > sg.c0) { refill_send(); if (MC) refill_keep(); }
                    mbar_wait((vfull ^ 16) + rv.s * 8, rv.ph);
                    TRACE(24);
                    wg_wait<0>();
                    pin(o); pin(S0); pin(S1);
                    TRACE(25);
                    cvt_state(S1, fr);
                    if (__builtin_expect(p2, 0)) scale_state(S1, st + ST_VEC + VEC_P2 + vq);
                    pin(S1); pin(fr);
                    wg_fence();
                    mma_kv(S1, pk);
                    {
                        const uint32_t stg = sm + OFF_V + rv.s * V_BYTES + ps * PANEL;
#pragma unroll
                        for (int i = 0; i < 4; i++)
                            sts128(stg + o_off + i * 2048, mul_bf16x2(pack_bf16(o[8 * i + 0], o[8 * i + 1]), SC2), mul_bf16x2(pack_bf16(o[8 * i + 2], o[8 * i + 3]), SC2),
                                   mul_bf16x2(pack_bf16(o[8 * i + 4], o[8 * i + 5]), SC2), mul_bf16x2(pack_bf16(o[8 * i + 6], o[8 * i + 7]), SC2));
                    }
                    auto ship = [&]() {
                        const uint32_t stg = sm + OFF_V + rv.s * V_BYTES + ps * PANEL;
                        fence_async();
                        __syncwarp();
                        if (elect_one()) mbar_arrive(vfree + rv.s * 8);
                        if (w == 2) {
                            mbar_wait2(vfree + rv.s * 8, rv.ph, BAR(B_INFREE + wg), xph ^ 1);
                            fence_acq_cluster();
                            if (elect_one())
                                asm volatile("cp.async.bulk.shared::cluster.shared::cta.mbarrier::complete_tx::bytes [%0], [%1], %2, [%3];"
                                             ::"r"(mapa(inbox, rank ^ 1)), "r"(stg), "n"(PANEL), "r"(mapa(BAR(B_INFULL + wg), rank ^ 1)) : "memory");
                            __syncwarp();
                        }
                        if (!MC && wg == 1 && c > sg.c0) refill_keep();
                    };
                    if (!(OPT & 1)) ship();
                    TRACE(26);
                    pin(o);
                    wg_fence();
                    mma_qs();
                    mma_av(pk);
                    wg_commit();
                    if (OPT & 1) ship();
                    rs.next<NST>(); rv.next<NVS>(); n++;
                    TRACE(19);
                    const uint32_t vn = sm + OFF_ST + rs.s * ST_BYTES + ST_VEC;
                    if (c + 1 < sg.c1) mbar_wait3(BAR(B_INFULL + wg), xph, BAR(B_QK + rs.s), rs.ph, vfull + rv.s * 8, rv.ph);
                    else mbar_wait(BAR(B_INFULL + wg), xph);
                    fence_acq_cluster();
#pragma unroll
                    for (int i = 0; i < PI_EARLY; i++) pi[i] = lds128(inbox + o_off + i * 2048);
                    TRACE(21);
                    wg_wait<0>();
                    pin(o); pin(S1);
                    TRACE(22);
#pragma unroll
                    for (int i = PI_EARLY; i < 4; i++) pi[i] = lds128(inbox + o_off + i * 2048);
                    load_vec(p, vn + VEC_P1 + vq);
                    flag = lds32(vn + VEC_FLAG + (opaque_tid() >> 10));
#pragma unroll
                    for (int i = 0; i < 4; i++) {
                        pi[i].x = fma_bf16x2(pack_bf16(o[8 * i + 0], o[8 * i + 1]), SC2, pi[i].x);
                        pi[i].y = fma_bf16x2(pack_bf16(o[8 * i + 2], o[8 * i + 3]), SC2, pi[i].y);
                        pi[i].z = fma_bf16x2(pack_bf16(o[8 * i + 4], o[8 * i + 5]), SC2, pi[i].z);
                        pi[i].w = fma_bf16x2(pack_bf16(o[8 * i + 6], o[8 * i + 7]), SC2, pi[i].w);
                    }
                    xph ^= 1;
                }
                stage_o();
                staged();
                if (wg == 1) {
                    duty_top(sg.c1 - 1, true);
                    if (!(PRO & 4) || si + 1 < nseg) { refill_keep(); refill_send(); }
                }
                TRACE(30);
            }
        }
        TRACE(40);
        if (elect_one()) asm volatile("cp.async.bulk.wait_group.read 0;" ::: "memory");
        __syncwarp();
        if (!synced) asm volatile("barrier.cluster.wait.acquire.aligned;" ::: "memory");
        asm volatile("barrier.cluster.arrive.relaxed.aligned;" ::: "memory");
        asm volatile("barrier.cluster.wait.acquire.aligned;" ::: "memory");
        if (tid == 0) p_epoch[blockIdx.x] = lds32(BAR(B_TAG)) ^ 1;
        TRACE_GT(1);
    }
}

typedef CUresult (*EncodeFn)(CUtensorMap*, CUtensorMapDataType, cuuint32_t, void*, const cuuint64_t*, const cuuint64_t*,
                             const cuuint32_t*, const cuuint32_t*, CUtensorMapInterleave, CUtensorMapSwizzle,
                             CUtensorMapL2promotion, CUtensorMapFloatOOBfill);

void make_map(EncodeFn enc, CUtensorMap* tm, const void* ptr, int panels) {
    cuuint64_t gd[3] = {64, (cuuint64_t)H_ * T_, 4};
    cuuint64_t gs[2] = {D_ * 2, 128};
    cuuint32_t bd[3] = {64, CH, (cuuint32_t)panels};
    cuuint32_t es[3] = {1, 1, 1};
    enc(tm, CU_TENSOR_MAP_DATA_TYPE_BFLOAT16, 3, const_cast<void*>(ptr), gd, gs, bd, es, CU_TENSOR_MAP_INTERLEAVE_NONE,
        CU_TENSOR_MAP_SWIZZLE_128B, CU_TENSOR_MAP_L2_PROMOTION_L2_256B, CU_TENSOR_MAP_FLOAT_OOB_FILL_NONE);
}

}

extern "C" void kernel_launch(void* const* d_in, const int* in_sizes, int n_in, void* d_out, int out_size) {
    (void)in_sizes; (void)n_in; (void)out_size;
    static EncodeFn enc = nullptr;
    static void *p_state = nullptr, *p_epoch = nullptr, *p_fb = nullptr;
    if (!enc) {
        cudaGetSymbolAddress(&p_state, g_state);
        cudaGetSymbolAddress(&p_epoch, g_epoch);
        cudaGetSymbolAddress(&p_fb, g_fb);
        void* fn = nullptr;
        cudaDriverEntryPointQueryResult qr;
        cudaGetDriverEntryPoint("cuTensorMapEncodeTiled", &fn, cudaEnableDefault, &qr);
        enc = (EncodeFn)fn;
        cudaFuncSetAttribute(gla_kernel, cudaFuncAttributeMaxDynamicSharedMemorySize, SMEM_ALLOC);
    }
    CUtensorMap tq, tk, tv, tg, to;
    make_map(enc, &tq, d_in[0], 2);
    make_map(enc, &tk, d_in[1], 2);
    make_map(enc, &tv, d_in[2], 1);
    make_map(enc, &tg, d_in[3], 2);
    make_map(enc, &to, d_out, 1);

    const char* plan = "F0-3,S17-24,F24-29;S0-3,F3-8,S25-29,F29-32;S3-8,F8-17;S8-17,F17-24;"
                       "F0-4,S21-27,F27-32;S0-4,F4-14;S5-14,F14-21;S14-21,F21-27";
    Sched sc = {};
    {
        int p = 0, slots = 0;
        const char* c = plan;
        for (int i = 0; i < NCHUNK; i++) sc.pub[0][i] = sc.pub[1][i] = -1;
        while (p < 8) {
            const int full = (*c++ == 'F');
            int c0 = 0, c1 = 0;
            while (*c >= '0' && *c <= '9') c0 = c0 * 10 + (*c++ - '0');
            c++;
            while (*c >= '0' && *c <= '9') c1 = c1 * 10 + (*c++ - '0');
            int8_t* pub = sc.pub[p >> 2];
            if (!full && c0 > 0 && pub[c0] < 0) pub[c0] = (int8_t)slots++;
            Seg& sg = sc.seg[p][sc.nseg[p]++];
            sg.full = (int8_t)full; sg.c0 = (int8_t)c0; sg.c1 = (int8_t)c1; sg.comb = (full || c0 == 0) ? (int8_t)16 : pub[c0];
            if (*c != ',') { p++; if (p == 4) slots = 0; }
            c = *c ? c + 1 : plan;
        }
    }

    for (int p = 0; p < 8; p++) {
        int n = 0;
        for (int i = 0; i < sc.nseg[p]; i++)
            for (int c = sc.seg[p][i].c0; c < sc.seg[p][i].c1; c++) sc.seq[p][n++] = (int8_t)(c | (sc.seg[p][i].full << 6));
        while (n < MAXSEQ) sc.seq[p][n++] = -1;
    }
    gla_kernel<<<128, 384, SMEM_ALLOC>>>(tq, tk, tg, tv, to, sc, (const __nv_bfloat16*)d_in[0], (const __nv_bfloat16*)d_in[1],
                                         (const __nv_bfloat16*)d_in[3], (const __nv_bfloat16*)d_in[2], (uint4*)p_state,
                                         (unsigned int*)p_epoch, (float*)p_fb);
}
```
